```python
import torch

def _softmax(x, axis=-1):
    return torch.softmax(x, dim=axis)
def _gelu(x):
    return torch.nn.functional.gelu(x, approximate="tanh")
def _silu(x):
    return torch.nn.functional.silu(x)
def _sigmoid(x):
    return torch.sigmoid(x)
def _layernorm(x, axis=-1, eps=1e-5):
    m = x.mean(dim=axis, keepdim=True)
    v = x.var(dim=axis, keepdim=True, unbiased=False)
    return (x - m) / torch.sqrt(v + eps)
def _scatter_add(tgt, idx, src, axis=0):
    return tgt.clone().index_add_(axis, idx, src)
def _segment_sum(src, seg, n):
    out = torch.zeros((n,) + src.shape[1:], dtype=src.dtype)
    return out.index_add_(0, seg, src)
def _pad(x, pw):
    flat = tuple(v for pair in reversed(pw) for v in pair)
    return torch.nn.functional.pad(x, flat)

kernel_name = 'standalone__window_attn_swin__vision'

def setup_inputs():

    _w = (lambda a: (lambda t: t.to(torch.bfloat16) if t.is_floating_point() else t)(torch.as_tensor(a)))
    H = W = 384
    C = 192
    ws = 8
    nh = 4
    shift = ws // 2
    coords = torch.stack(torch.meshgrid(torch.arange(ws), torch.arange(ws), indexing='ij'), 0).reshape(2, -1)
    rel = coords[:, :, None] - coords[:, None, :]
    rel[0] += ws - 1
    rel[1] += ws - 1
    rel[0] *= 2 * ws - 1
    rp_idx = rel.sum(0).to(torch.int64)
    img_mask = torch.zeros((1, H, W, 1), dtype=float)
    cnt = 0
    for hs in (slice(0, H - ws), slice(H - ws, H - shift), slice(H - shift, H)):
        for vs in (slice(0, W - ws), slice(W - ws, W - shift), slice(W - shift, W)):
            img_mask[:, hs, vs, :] = cnt
            cnt += 1
    mw = img_mask.reshape(1, H // ws, ws, W // ws, ws, 1).permute(0, 1, 3, 2, 4, 5).reshape(-1, ws * ws)
    am = mw[:, :, None] - mw[:, None, :]
    attn_mask = torch.where(am != 0, -100.0, 0.0).to(float)
    return {
        "x": _w((lambda *s: torch.randn(*s, dtype=torch.bfloat16) * 1.6)(1, H, W, C)),
        "wqkv": _w((lambda *s: torch.randn(*s, dtype=torch.bfloat16) * 1.6)(C, 3 * C) * 0.02),
        "wo": _w((lambda *s: torch.randn(*s, dtype=torch.bfloat16) * 0.05)(C, C) * 0.02),
        "rpb": _w((lambda *s: torch.randn(*s, dtype=torch.bfloat16) * 0.2)((2 * ws - 1) * (2 * ws - 1), nh)),
        "rp_idx": _w(rp_idx),
        "attn_mask": _w(attn_mask),
    }

def reference(x, wqkv, wo, rpb, rp_idx, attn_mask):
    B, H, W, C = x.shape
    N = rp_idx.shape[0]
    ws = int(round(N ** 0.5))
    nh = rpb.shape[-1]
    hd = C // nh
    shift = ws // 2
    xs = torch.roll(x, (-shift, -shift), (1, 2))
    nWh = H // ws
    nWw = W // ws
    xw = (lambda x, *d: x.permute(*d))(xs.reshape(B, nWh, ws, nWw, ws, C), 0, 1, 3, 2, 4, 5).reshape(B * nWh * nWw, N, C)
    qkv = (lambda x, *d: x.permute(*d))(torch.einsum('wnc,cd->wnd', xw, wqkv).reshape(-1, N, 3, nh, hd), 2, 0, 3, 1, 4)
    q, k, v = qkv[0], qkv[1], qkv[2]
    attn = torch.einsum('whid,whjd->whij', q, k) * (hd ** -0.5)
    bias = (lambda x, *d: x.permute(*d))(rpb[rp_idx.reshape(-1)].reshape(N, N, nh), 2, 0, 1)
    attn = attn + bias[None, :, :, :]
    attn = (attn.reshape(B, nWh * nWw, nh, N, N) + attn_mask[None, :, None, :, :]).reshape(-1, nh, N, N)
    attn = _softmax(attn, axis=-1)
    out = (lambda x, *d: x.permute(*d))(torch.einsum('whij,whjd->whid', attn, v), 0, 2, 1, 3).reshape(-1, N, C)
    out = torch.einsum('wnc,cd->wnd', out, wo)
    out = (lambda x, *d: x.permute(*d))(out.reshape(B, nWh, nWw, ws, ws, C), 0, 1, 3, 2, 4, 5).reshape(B, H, W, C)
    return torch.roll(out, (shift, shift), (1, 2))
```

```cpp
#include <cuda_runtime.h>
#include <cuda_bf16.h>
#include <cuda.h>
#include <stdint.h>
#include <math.h>

namespace {
__device__ __forceinline__ void wgmma_n64(float (&d)[32], uint32_t a0, uint32_t a1, uint32_t a2, uint32_t a3, uint64_t descB, int scaleD) {
  asm volatile("{\n.reg .pred p;\n"
    "setp.ne.b32 p, %37, 0;\n"
    "wgmma.mma_async.sync.aligned.m64n64k16.f32.bf16.bf16 "
    "{%0, %1, %2, %3, %4, %5, %6, %7, %8, %9, %10, %11, %12, %13, %14, %15, %16, %17, %18, %19, %20, %21, %22, %23, %24, %25, %26, %27, %28, %29, %30, %31}, "
    "{%32, %33, %34, %35}, %36, p, 1, 1, 0;\n}\n"
    : "+f"(d[0]), "+f"(d[1]), "+f"(d[2]), "+f"(d[3]), "+f"(d[4]), "+f"(d[5]), "+f"(d[6]), "+f"(d[7]), "+f"(d[8]), "+f"(d[9]), "+f"(d[10]), "+f"(d[11]), "+f"(d[12]), "+f"(d[13]), "+f"(d[14]), "+f"(d[15]), "+f"(d[16]), "+f"(d[17]), "+f"(d[18]), "+f"(d[19]), "+f"(d[20]), "+f"(d[21]), "+f"(d[22]), "+f"(d[23]), "+f"(d[24]), "+f"(d[25]), "+f"(d[26]), "+f"(d[27]), "+f"(d[28]), "+f"(d[29]), "+f"(d[30]), "+f"(d[31])
    : "r"(a0), "r"(a1), "r"(a2), "r"(a3), "l"(descB), "r"(scaleD));
}

__device__ __forceinline__ void wgmma_n56(float (&d)[28], uint32_t a0, uint32_t a1, uint32_t a2, uint32_t a3, uint64_t descB, int scaleD) {
  asm volatile("{\n.reg .pred p;\n"
    "setp.ne.b32 p, %33, 0;\n"
    "wgmma.mma_async.sync.aligned.m64n56k16.f32.bf16.bf16 "
    "{%0, %1, %2, %3, %4, %5, %6, %7, %8, %9, %10, %11, %12, %13, %14, %15, %16, %17, %18, %19, %20, %21, %22, %23, %24, %25, %26, %27}, "
    "{%28, %29, %30, %31}, %32, p, 1, 1, 1;\n}\n"
    : "+f"(d[0]), "+f"(d[1]), "+f"(d[2]), "+f"(d[3]), "+f"(d[4]), "+f"(d[5]), "+f"(d[6]), "+f"(d[7]), "+f"(d[8]), "+f"(d[9]), "+f"(d[10]), "+f"(d[11]), "+f"(d[12]), "+f"(d[13]), "+f"(d[14]), "+f"(d[15]), "+f"(d[16]), "+f"(d[17]), "+f"(d[18]), "+f"(d[19]), "+f"(d[20]), "+f"(d[21]), "+f"(d[22]), "+f"(d[23]), "+f"(d[24]), "+f"(d[25]), "+f"(d[26]), "+f"(d[27])
    : "r"(a0), "r"(a1), "r"(a2), "r"(a3), "l"(descB), "r"(scaleD));
}

__device__ __forceinline__ void wgmma_n96(float (&d)[48], uint32_t a0, uint32_t a1, uint32_t a2, uint32_t a3, uint64_t descB, int scaleD) {
  asm volatile("{\n.reg .pred p;\n"
    "setp.ne.b32 p, %53, 0;\n"
    "wgmma.mma_async.sync.aligned.m64n96k16.f32.bf16.bf16 "
    "{%0, %1, %2, %3, %4, %5, %6, %7, %8, %9, %10, %11, %12, %13, %14, %15, %16, %17, %18, %19, %20, %21, %22, %23, %24, %25, %26, %27, %28, %29, %30, %31, %32, %33, %34, %35, %36, %37, %38, %39, %40, %41, %42, %43, %44, %45, %46, %47}, "
    "{%48, %49, %50, %51}, %52, p, 1, 1, 1;\n}\n"
    : "+f"(d[0]), "+f"(d[1]), "+f"(d[2]), "+f"(d[3]), "+f"(d[4]), "+f"(d[5]), "+f"(d[6]), "+f"(d[7]), "+f"(d[8]), "+f"(d[9]), "+f"(d[10]), "+f"(d[11]), "+f"(d[12]), "+f"(d[13]), "+f"(d[14]), "+f"(d[15]), "+f"(d[16]), "+f"(d[17]), "+f"(d[18]), "+f"(d[19]), "+f"(d[20]), "+f"(d[21]), "+f"(d[22]), "+f"(d[23]), "+f"(d[24]), "+f"(d[25]), "+f"(d[26]), "+f"(d[27]), "+f"(d[28]), "+f"(d[29]), "+f"(d[30]), "+f"(d[31]), "+f"(d[32]), "+f"(d[33]), "+f"(d[34]), "+f"(d[35]), "+f"(d[36]), "+f"(d[37]), "+f"(d[38]), "+f"(d[39]), "+f"(d[40]), "+f"(d[41]), "+f"(d[42]), "+f"(d[43]), "+f"(d[44]), "+f"(d[45]), "+f"(d[46]), "+f"(d[47])
    : "r"(a0), "r"(a1), "r"(a2), "r"(a3), "l"(descB), "r"(scaleD));
}
}
#include <limits.h>


namespace {

constexpr int IMG = 384;
constexpr int CH = 192;
constexpr int NWIN = 2304;
constexpr int NWW = 48;
constexpr int NCLUSTERS = 66;
constexpr int NWG = 3;
constexpr int NTHREADS = NWG * 128;
constexpr int WSTEP = NWG * NCLUSTERS;

constexpr uint32_t SLAB = 36864;
constexpr uint32_t OFF_WK = 0;
constexpr uint32_t OFF_WV = SLAB;
constexpr uint32_t OFF_WQ = 2 * SLAB;
constexpr uint32_t OFF_WO = 3 * SLAB;
constexpr uint32_t OFF_WG = 4 * SLAB;
constexpr uint32_t OFF_VR = 12288;
constexpr uint32_t VTB = 13 * 128;
constexpr uint32_t WG_BYTES = OFF_VR + 8 * VTB;
constexpr uint32_t OFF_TBL = OFF_WG + NWG * WG_BYTES;
constexpr uint32_t OFF_BAR = OFF_TBL + 1024;
constexpr uint32_t BAR_W = OFF_BAR;
constexpr uint32_t BAR_WQS = OFF_BAR + 24;
constexpr uint32_t BAR_WO = OFF_BAR + 32;
constexpr uint32_t BAR_BIAS = OFF_BAR + 40;
constexpr uint32_t BAR_BIASDONE = OFF_BAR + 48;
constexpr uint32_t BAR_X = OFF_BAR + 64;
constexpr uint32_t BAR_KF = OFF_BAR + 160;
constexpr uint32_t SMEM_BYTES = OFF_BAR + 232;

constexpr int BAR_ID_WG = 1;
constexpr int BAR_ID_TOKEN = 4;
constexpr int BAR_ID_GAP = 10;

constexpr int LDSM_EARLY = 4;
constexpr int PASS_KSTEP = 9;

constexpr float SCALE = 0.14433756729740643f;
constexpr float LOG2E = 1.4426950408889634f;

__device__ __forceinline__ void wg_fence() { asm volatile("wgmma.fence.sync.aligned;" ::: "memory"); }
__device__ __forceinline__ void wg_commit() { asm volatile("wgmma.commit_group.sync.aligned;" ::: "memory"); }
template <int N> __device__ __forceinline__ void wg_wait() { asm volatile("wgmma.wait_group.sync.aligned %0;" ::"n"(N) : "memory"); }
template <int N> __device__ __forceinline__ void pin(float (&d)[N]) {
#pragma unroll
  for (int i = 0; i < N; i++) asm volatile("" : "+f"(d[i])::"memory");
}

__device__ __forceinline__ uint32_t desc_lo(uint32_t addr, uint32_t lbo) { return ((addr & 0x3FFFF) >> 4) | ((lbo >> 4) << 16); }
__device__ __forceinline__ uint64_t mk_desc(uint32_t lo, uint32_t hi) {
  uint64_t d;
  asm("mov.b64 %0, {%1, %2};" : "=l"(d) : "r"(lo), "r"(hi));
  return d;
}
constexpr uint32_t HI_W = (512 >> 4) | (2u << 30);
constexpr uint32_t HI_K = 1536 >> 4;
constexpr uint32_t HI_V = 128 >> 4;

__device__ __forceinline__ uint32_t pack_bf16(float lo, float hi) {
  uint32_t r;
  asm("cvt.rn.bf16x2.f32 %0, %1, %2;" : "=r"(r) : "f"(hi), "f"(lo));
  return r;
}
__device__ __forceinline__ float bf_lo(uint32_t v) { return __uint_as_float(v << 16); }
__device__ __forceinline__ float bf_hi(uint32_t v) { return __uint_as_float(v & 0xffff0000u); }
__device__ __forceinline__ uint32_t add_bf16x2(uint32_t a, uint32_t b) {
  uint32_t r;
  asm("add.rn.bf16x2 %0, %1, %2;" : "=r"(r) : "r"(a), "r"(b));
  return r;
}
__device__ __forceinline__ float rcp(float x) {
  float y;
  asm("rcp.approx.ftz.f32 %0, %1;" : "=f"(y) : "f"(x));
  return y;
}
__device__ __forceinline__ float ex2(float x) {
  float y;
  asm("ex2.approx.ftz.f32 %0, %1;" : "=f"(y) : "f"(x));
  return y;
}

__device__ __forceinline__ void ldg_v4(uint32_t (&r)[4], const void* p) {
  asm volatile("ld.global.nc.v4.b32 {%0,%1,%2,%3}, [%4];" : "=r"(r[0]), "=r"(r[1]), "=r"(r[2]), "=r"(r[3]) : "l"(p));
}
__device__ __forceinline__ void ldg_stream(uint32_t (&r)[4], const void* p) {
  asm volatile("ld.global.nc.L1::no_allocate.v4.b32 {%0,%1,%2,%3}, [%4];" : "=r"(r[0]), "=r"(r[1]), "=r"(r[2]), "=r"(r[3]) : "l"(p));
}
__device__ __forceinline__ void lds_v4(uint32_t (&r)[4], uint32_t addr) {
  asm volatile("ld.shared.v4.b32 {%0,%1,%2,%3}, [%4];" : "=r"(r[0]), "=r"(r[1]), "=r"(r[2]), "=r"(r[3]) : "r"(addr));
}
__device__ __forceinline__ uint32_t lds_32(uint32_t addr) {
  uint32_t v;
  asm volatile("ld.shared.b32 %0, [%1];" : "=r"(v) : "r"(addr));
  return v;
}
__device__ __forceinline__ void sts_32(uint32_t addr, uint32_t v) { asm volatile("st.shared.b32 [%0], %1;" ::"r"(addr), "r"(v) : "memory"); }
__device__ __forceinline__ void stsm_x4(uint32_t addr, uint32_t a, uint32_t b, uint32_t c, uint32_t d) {
  asm volatile("stmatrix.sync.aligned.m8n8.x4.shared.b16 [%0], {%1,%2,%3,%4};" ::"r"(addr), "r"(a), "r"(b), "r"(c), "r"(d) : "memory");
}
__device__ __forceinline__ void stsm_x2(uint32_t addr, uint32_t a, uint32_t b) {
  asm volatile("stmatrix.sync.aligned.m8n8.x2.shared.b16 [%0], {%1,%2};" ::"r"(addr), "r"(a), "r"(b) : "memory");
}
struct TrueTag { static constexpr bool value = true; };
struct FalseTag { static constexpr bool value = false; };
__device__ __forceinline__ void ldsm_x4(uint32_t (&r)[4], uint32_t addr) {
  asm volatile("ldmatrix.sync.aligned.m8n8.x4.shared.b16 {%0,%1,%2,%3}, [%4];" : "=r"(r[0]), "=r"(r[1]), "=r"(r[2]), "=r"(r[3]) : "r"(addr));
}
__device__ __forceinline__ void fence_async_smem() { asm volatile("fence.proxy.async.shared::cta;" ::: "memory"); }
__device__ __forceinline__ void wg_bar(int id) { asm volatile("bar.sync %0, 128;" ::"r"(id) : "memory"); }
__device__ __forceinline__ void order_wait(int id) { asm volatile("bar.sync %0, 256;" ::"r"(id) : "memory"); }
__device__ __forceinline__ void order_pass(int id) { asm volatile("bar.arrive %0, 256;" ::"r"(id) : "memory"); }

__device__ __forceinline__ uint32_t map_peer(uint32_t addr, uint32_t rank) {
  uint32_t r;
  asm("mapa.shared::cluster.u32 %0, %1, %2;" : "=r"(r) : "r"(addr), "r"(rank));
  return r;
}
__device__ __forceinline__ void mbar_init(uint32_t bar, uint32_t count) {
  asm volatile("mbarrier.init.shared::cta.b64 [%0], %1;" ::"r"(bar), "r"(count) : "memory");
}
__device__ __forceinline__ void mbar_expect_tx(uint32_t bar, uint32_t bytes) {
  asm volatile("mbarrier.arrive.expect_tx.shared::cta.b64 _, [%0], %1;" ::"r"(bar), "r"(bytes) : "memory");
}
__device__ __forceinline__ void mbar_arrive_remote(uint32_t bar) {
  asm volatile("mbarrier.arrive.shared::cluster.b64 _, [%0];" ::"r"(bar) : "memory");
}
__device__ __forceinline__ void mbar_wait(uint32_t bar, uint32_t parity) {
  asm volatile(
      "{\n.reg .pred p;\n"
      "WAIT_LOOP:\n"
      "mbarrier.try_wait.parity.shared::cta.b64 p, [%0], %1;\n"
      "@p bra WAIT_DONE;\n"
      "bra WAIT_LOOP;\n"
      "WAIT_DONE:\n}\n" ::"r"(bar), "r"(parity) : "memory");
}
__device__ __forceinline__ void st_async_v4(uint32_t addr, uint32_t a, uint32_t b, uint32_t c, uint32_t d, uint32_t bar) {
  asm volatile("st.async.weak.shared::cluster.mbarrier::complete_tx::bytes.v4.b32 [%0], {%1,%2,%3,%4}, [%5];" ::"r"(addr), "r"(a), "r"(b), "r"(c), "r"(d), "r"(bar) : "memory");
}
__device__ __forceinline__ void tma_2d(uint32_t dst, const CUtensorMap* map, int c0, int c1, uint32_t bar) {
  asm volatile("cp.async.bulk.tensor.2d.shared::cluster.global.mbarrier::complete_tx::bytes [%0], [%1, {%2, %3}], [%4];" ::"r"(dst), "l"(map), "r"(c0), "r"(c1), "r"(bar) : "memory");
}
__device__ __forceinline__ void tma_5d(uint32_t dst, const CUtensorMap* map, int c0, int c1, int c2, int c3, int c4, uint32_t bar) {
  asm volatile("cp.async.bulk.tensor.5d.shared::cluster.global.mbarrier::complete_tx::bytes [%0], [%1, {%2, %3, %4, %5, %6}], [%7];" ::"r"(dst), "l"(map),
               "r"(c0), "r"(c1), "r"(c2), "r"(c3), "r"(c4), "r"(bar) : "memory");
}
__device__ __forceinline__ void tma_store_4d(const CUtensorMap* map, uint32_t src, int c0, int c1, int c2, int c3) {
  asm volatile("cp.async.bulk.tensor.4d.global.shared::cta.bulk_group [%0, {%2, %3, %4, %5}], [%1];" ::"l"(map), "r"(src), "r"(c0), "r"(c1), "r"(c2), "r"(c3) : "memory");
}
__device__ __forceinline__ void tma_prefetch_5d(const CUtensorMap* map, int c0, int c1, int c2, int c3, int c4) {
  asm volatile("cp.async.bulk.prefetch.tensor.5d.L2.global [%0, {%1, %2, %3, %4, %5}];" ::"l"(map), "r"(c0), "r"(c1), "r"(c2), "r"(c3), "r"(c4) : "memory");
}
__device__ __forceinline__ void bulk_prefetch(const void* p, uint32_t bytes) {
  asm volatile("cp.async.bulk.prefetch.L2.global [%0], %1;" ::"l"(p), "r"(bytes) : "memory");
}
__device__ __forceinline__ bool elect_one() {
  uint32_t p;
  asm volatile("{\n.reg .pred P;\nelect.sync _|P, 0xffffffff;\nselp.b32 %0, 1, 0, P;\n}" : "=r"(p));
  return p != 0;
}
__device__ __forceinline__ void mbar_arrive(uint32_t bar) {
  asm volatile("mbarrier.arrive.shared::cta.b64 _, [%0];" ::"r"(bar) : "memory");
}
__device__ __forceinline__ void sts_v4(uint32_t addr, uint32_t a, uint32_t b, uint32_t c, uint32_t d) {
  asm volatile("st.shared.v4.b32 [%0], {%1,%2,%3,%4};" ::"r"(addr), "r"(a), "r"(b), "r"(c), "r"(d) : "memory");
}
__device__ __forceinline__ uint32_t opaque(uint32_t v) { asm volatile("" : "+r"(v)); return v; }

__device__ __forceinline__ int tok_i(int warp, int g) { return 4 * (warp >> 1) + (g >> 1); }
__device__ __forceinline__ int tok_j(int warp, int g) { return 4 * (warp & 1) + (g & 1); }

__device__ __forceinline__ int quad_row(int wi, int warp) { int r = wi * 8 + 4 + 4 * (warp >> 1); return r >= IMG ? r - IMG : r; }
__device__ __forceinline__ int quad_col(int wj, int warp) { int c = wj * 8 + 4 + 4 * (warp & 1); return c >= IMG ? c - IMG : c; }

__device__ __forceinline__ void stage_x(const CUtensorMap* tmx, int wi, int wj, int warp, uint32_t kbase, uint32_t bar) {
  const int r = quad_row(wi, warp), c2 = quad_col(wj, warp) >> 1;
  mbar_expect_tx(bar, 6144);
  tma_5d(kbase + warp * 3072, tmx, 0, 0, r, c2, 0, bar);
  tma_5d(kbase + OFF_VR + warp * 3072, tmx, 0, 0, r, c2 + 1, 0, bar);
}

__global__ void __cluster_dims__(2, 1, 1) __launch_bounds__(NTHREADS, 1)
swin_attn_kernel(const __grid_constant__ CUtensorMap tmx, const __grid_constant__ CUtensorMap tmw, const __grid_constant__ CUtensorMap tmo,
                 const __grid_constant__ CUtensorMap tmy0, const __grid_constant__ CUtensorMap tmy1,
                 const __nv_bfloat16* __restrict__ rpb, const int* __restrict__ rp_idx, const __nv_bfloat16* __restrict__ mask) {
  extern __shared__ __align__(1024) uint8_t smem_raw[];
  const uint32_t sb = (uint32_t)__cvta_generic_to_shared(smem_raw);
  const int wg = __shfl_sync(0xffffffffu, threadIdx.x >> 7, 0);
  const int warp = __shfl_sync(0xffffffffu, (threadIdx.x >> 5) & 3, 0);
  uint32_t rank;
  asm("mov.u32 %0, %%cluster_ctarank;" : "=r"(rank));
  const uint32_t peer = rank ^ 1;
  const uint32_t rt0 = rank >> 1;
  const int wg_next = wg == NWG - 1 ? 0 : wg + 1;
  const uint32_t kbase = sb + OFF_WG + wg * WG_BYTES;
  const uint32_t bar_x = sb + BAR_X + (wg * 4 + warp) * 8;
  const uint32_t bar_kfree = sb + BAR_KF + wg * 24;
  const uint32_t bar_ofull = bar_kfree + 8;
  int w = wg * NCLUSTERS + (blockIdx.x >> 1);
  int wi = w / NWW, wj = w - wi * NWW;

  const int lane = threadIdx.x & 31, g = lane >> 2, q = lane & 3;
  if (threadIdx.x == 0) {
    for (int i = 0; i < 3; i++) mbar_init(sb + BAR_W + i * 8, 1);
    mbar_init(sb + BAR_WQS, 4);
    mbar_init(sb + BAR_WO, 1);
    mbar_init(sb + BAR_BIAS, 4);
    mbar_init(sb + BAR_BIASDONE, 12);
    for (int i = 0; i < 12; i++) mbar_init(sb + BAR_X + i * 8, 1);
    for (int i = 0; i < NWG; i++) {
      mbar_init(sb + BAR_KF + i * 24, 4);
      mbar_init(sb + BAR_KF + i * 24 + 8, 1);
      mbar_init(sb + BAR_KF + i * 24 + 16, 1);
    }
    asm volatile("fence.mbarrier_init.release.cluster;" ::: "memory");
    fence_async_smem();
    mbar_expect_tx(sb + BAR_W, SLAB);
#pragma unroll
    for (int cg = 0; cg < 3; cg++) tma_2d(sb + OFF_WK + cg * 12288, &tmw, CH + 96 * rank + 32 * cg, 0, sb + BAR_W);
  }
  uint32_t bz[2][2][2][4];
  const uint32_t bias_tbl = sb + OFF_WG + 2 * WG_BYTES + (threadIdx.x & 127) * 16;
  auto fetch_bias = [&]() {
    mbar_wait(sb + BAR_BIAS, 0);
#pragma unroll
    for (int c = 0; c < 8; c++) lds_v4(bz[c >> 2][(c >> 1) & 1][c & 1], bias_tbl + c * 2048);
    uint32_t dep = 0;
#pragma unroll
    for (int c = 0; c < 8; c++) dep |= bz[c >> 2][(c >> 1) & 1][c & 1][0];
    dep = __reduce_or_sync(0xffffffffu, dep);
    if (lane == 0) mbar_arrive(sb + BAR_BIASDONE + (dep & rt0));
  };
  if (wg == 2) {
    const int t = threadIdx.x & 127;
    uint32_t idx[2][2][8];
    const int* ip = rp_idx + (8 * tok_i(warp, g) + tok_j(warp, g)) * 64 + 8 * q;
#pragma unroll
    for (int rho = 0; rho < 2; rho++)
#pragma unroll
      for (int a = 0; a < 2; a++) {
        uint32_t t0[4], t1[4];
        ldg_v4(t0, ip + rho * 128 + a * 32);
        ldg_v4(t1, ip + rho * 128 + a * 32 + 4);
#pragma unroll
        for (int e = 0; e < 4; e++) { idx[rho][a][e] = t0[e]; idx[rho][a][4 + e] = t1[e]; }
      }
    const uint32_t tb0 = *reinterpret_cast<const uint32_t*>(rpb + t * 4 + 2 * rank);
    const uint32_t tb1 = t < 97 ? *reinterpret_cast<const uint32_t*>(rpb + (128 + t) * 4 + 2 * rank) : 0u;
    __syncthreads();
    asm volatile("barrier.cluster.arrive.relaxed.aligned;" ::: "memory");
    order_pass(BAR_ID_TOKEN);
    sts_32(sb + OFF_TBL + t * 4, tb0);
    sts_32(sb + OFF_TBL + (128 + t) * 4, tb1);
    wg_bar(BAR_ID_WG + wg);
#pragma unroll
    for (int rho = 0; rho < 2; rho++)
#pragma unroll
      for (int a = 0; a < 2; a++) {
        uint32_t h0[4], h1[4];
#pragma unroll
        for (int m = 0; m < 4; m++) {
          int i0 = (int)idx[rho][a][2 * m], i1 = (int)idx[rho][a][2 * m + 1];
          if (i0 < 0) i0 += 225;
          if (i1 < 0) i1 += 225;
          const uint32_t b0 = lds_32(sb + OFF_TBL + i0 * 4), b1 = lds_32(sb + OFF_TBL + i1 * 4);
          h0[m] = __byte_perm(b0, b1, 0x5410);
          h1[m] = __byte_perm(b0, b1, 0x7632);
        }
        sts_v4(bias_tbl + (rho * 2 + a) * 2048, h0[0], h0[1], h0[2], h0[3]);
        sts_v4(bias_tbl + (4 + rho * 2 + a) * 2048, h1[0], h1[1], h1[2], h1[3]);
      }
    __syncwarp();
    if (lane == 0) mbar_arrive(sb + BAR_BIAS);
    fetch_bias();
    mbar_wait(sb + BAR_W + 16, 0);
#pragma unroll 6
    for (int it = 0; it < 18; it++) {
      const uint32_t a = sb + OFF_WQ + (it * 128 + t) * 16;
      uint32_t v[4];
      lds_v4(v, a);
#pragma unroll
      for (int e = 0; e < 4; e++) v[e] = pack_bf16(bf_lo(v[e]) * SCALE, bf_hi(v[e]) * SCALE);
      sts_v4(a, v[0], v[1], v[2], v[3]);
    }
    fence_async_smem();
    __syncwarp();
    if (lane == 0) mbar_arrive(sb + BAR_WQS);
    mbar_wait(sb + BAR_BIASDONE, 0);
    if (elect_one()) stage_x(&tmx, wi, wj, warp, kbase, bar_x);
  } else {
    __syncthreads();
    asm volatile("barrier.cluster.arrive.relaxed.aligned;" ::: "memory");
    if (wg == 0) {
      if (elect_one()) {
        stage_x(&tmx, wi, wj, warp, kbase, bar_x);
        if (warp == 0) {
          mbar_expect_tx(sb + BAR_W + 16, SLAB);
#pragma unroll
          for (int cg = 0; cg < 3; cg++) tma_2d(sb + OFF_WQ + cg * 12288, &tmw, 96 * rank + 32 * cg, 0, sb + BAR_W + 16);
          mbar_expect_tx(sb + BAR_W + 8, SLAB);
#pragma unroll
          for (int cg = 0; cg < 3; cg++) tma_2d(sb + OFF_WV + cg * 12288, &tmw, 2 * CH + 96 * rank + 32 * cg, 0, sb + BAR_W + 8);
        }
      }
    } else {
      mbar_wait(sb + BAR_W + 8, 0);
      if (elect_one()) stage_x(&tmx, wi, wj, warp, kbase, bar_x);
      if (warp == 0 && elect_one()) {
        mbar_expect_tx(sb + BAR_WO, SLAB);
#pragma unroll
        for (int cg = 0; cg < 3; cg++) tma_2d(sb + OFF_WO + cg * 12288, &tmo, 96 * rank + 32 * cg, 0, sb + BAR_WO);
      }
      fetch_bias();
    }
  }
  asm volatile("barrier.cluster.wait.aligned;" ::: "memory");

  const uint32_t ln_ld = opaque(kbase + warp * 3072 + ((lane >> 3) & 1) * OFF_VR + (lane & 7) * 128 + (((lane >> 4) ^ (lane & 7)) << 4));
  const uint32_t ln_stk = opaque(kbase + (2 * warp + ((lane >> 3) & 1)) * 1536 + (lane >> 4) * 128 + (lane & 7) * 16);
  const uint32_t ln_stv = opaque(kbase + OFF_VR + (2 * warp + ((lane >> 3) & 1)) * VTB + (lane >> 4) * 128 + (lane & 7) * 16);
  const uint32_t ln_mask = opaque(((8 * (g >> 1) + (g & 1)) * 64 + 8 * q) * 2);
  const uint32_t ln_oa = opaque(kbase + OFF_VR + warp * 3072 + ((lane & 7) + 8 * ((lane >> 3) & 1)) * 128 + (((lane >> 4) ^ (lane & 7)) << 4));
  const uint32_t ln_ob = opaque(kbase + OFF_VR + warp * 3072 + 2048 + ((lane & 7) + 8 * ((lane >> 3) & 1)) * 64 + (((lane >> 4) ^ ((lane >> 1) & 3)) << 4));
  const uint32_t ln_slot = opaque(kbase + warp * 3072 + lane * 16);
  uint32_t ob[24];
  auto stage_out = [&]() {
#pragma unroll
    for (int j = 0; j < 4; j++) stsm_x4(ln_oa ^ (32 * j), ob[4 * j], ob[4 * j + 1], ob[4 * j + 2], ob[4 * j + 3]);
#pragma unroll
    for (int j = 0; j < 2; j++) stsm_x4(ln_ob ^ (32 * j), ob[16 + 4 * j], ob[16 + 4 * j + 1], ob[16 + 4 * j + 2], ob[16 + 4 * j + 3]);
  };
  auto send_out = [&](int owi, int owj) {
    fence_async_smem();
    __syncwarp();
    if (elect_one()) {
      const int r = quad_row(owi, warp), c2 = quad_col(owj, warp) >> 1;
      tma_store_4d(&tmy0, kbase + OFF_VR + warp * 3072, 96 * rank, 0, r, c2);
      tma_store_4d(&tmy1, kbase + OFF_VR + warp * 3072 + 2048, 96 * rank + 64, 0, r, c2);
      asm volatile("cp.async.bulk.commit_group;" ::: "memory");
    }
  };
  auto store_out = [&](int owi, int owj) { stage_out(); send_out(owi, owj); };
  int pwi = 0, pwj = 0;
  uint32_t parity = 0;

  auto window = [&](auto first_tag) __attribute__((always_inline)) {
    constexpr bool FIRST = decltype(first_tag)::value;
    const uint64_t d_wk = mk_desc(desc_lo(sb + OFF_WK, 12288), HI_W + rt0);
    const uint64_t d_wv = d_wk + (OFF_WV >> 4), d_wq = d_wk + (OFF_WQ >> 4);
    const uint64_t d_wo_own = d_wk + ((OFF_WO >> 4) + rank * 384), d_wo_peer = d_wk + ((OFF_WO >> 4) + peer * 384);
    const uint64_t d_k = mk_desc(desc_lo(kbase, 128), HI_K + rt0);
    const uint64_t d_v = mk_desc(desc_lo(kbase + OFF_VR, VTB), HI_V + rt0);
    int nwi = wi + WSTEP / NWW, nwj = wj + WSTEP % NWW;
    if (nwj >= NWW) { nwj -= NWW; nwi++; }
    const bool has_next = w + WSTEP < NWIN;
    uint32_t af[12][4];
    if (elect_one()) {
      if (warp == 0) { mbar_expect_tx(bar_ofull, 6144); mbar_expect_tx(bar_ofull + 8, 6144); }
      if (has_next) {
        tma_prefetch_5d(&tmx, 0, 0, quad_row(nwi, warp), (quad_col(nwj, warp) >> 1) + rank, 0);
        if (warp == 0) bulk_prefetch(mask + (size_t)(w + WSTEP) * 4096 + rank * 2048, 4096);
      }
    }
    mbar_wait(bar_x, parity);
    {
      const uint32_t a = opaque(ln_ld);
#pragma unroll
      for (int ks = 0; ks < LDSM_EARLY; ks++) ldsm_x4(af[ks], (a ^ (32 * (ks & 3))) + (ks >> 2) * 1024);
    }
    order_wait(BAR_ID_TOKEN + wg);
    uint32_t qf[24];
    uint32_t mk[2][2][4];
    {
      float acc[48];
      auto issue = [&](uint64_t dl) {
        wg_fence();
#pragma unroll
        for (int ks = 0; ks < 12; ks++) wgmma_n96(acc, af[ks][0], af[ks][1], af[ks][2], af[ks][3], dl + ks * 64, ks != 0);
        wg_commit();
      };
      if (FIRST) mbar_wait(sb + BAR_W, 0);
      wg_fence();
#pragma unroll
      for (int ks = 0; ks < LDSM_EARLY; ks++) wgmma_n96(acc, af[ks][0], af[ks][1], af[ks][2], af[ks][3], d_wk + ks * 64, ks != 0);
      {
        const uint32_t a = opaque(ln_ld);
#pragma unroll
        for (int ks = LDSM_EARLY; ks < 12; ks++) ldsm_x4(af[ks], (a ^ (32 * (ks & 3))) + (ks >> 2) * 1024);
      }
      wg_fence();
#pragma unroll
      for (int ks = LDSM_EARLY; ks < 12; ks++) wgmma_n96(acc, af[ks][0], af[ks][1], af[ks][2], af[ks][3], d_wk + ks * 64, 1);
      wg_commit();
      if (!FIRST) stage_out();
      wg_wait<0>();
      pin(acc);
#pragma unroll
      for (int j = 0; j < 6; j++)
        stsm_x4(ln_stk + j * 256, pack_bf16(acc[8 * j], acc[8 * j + 1]), pack_bf16(acc[8 * j + 2], acc[8 * j + 3]),
                pack_bf16(acc[8 * j + 4], acc[8 * j + 5]), pack_bf16(acc[8 * j + 6], acc[8 * j + 7]));
      if (FIRST) mbar_wait(sb + BAR_W + 8, 0);
      issue(d_wv);
      if (!FIRST) send_out(pwi, pwj);
      if (!FIRST && elect_one()) asm volatile("cp.async.bulk.wait_group.read 0;" ::: "memory");
      wg_bar(BAR_ID_WG + wg);
      wg_wait<0>();
      pin(acc);
      if (w >= NCLUSTERS) order_pass(BAR_ID_GAP + wg);
#pragma unroll
      for (int j = 0; j < 6; j++)
        stsm_x4(ln_stv + j * 256 + (j >= 3 ? 128 : 0), pack_bf16(acc[8 * j], acc[8 * j + 1]), pack_bf16(acc[8 * j + 2], acc[8 * j + 3]),
                pack_bf16(acc[8 * j + 4], acc[8 * j + 5]), pack_bf16(acc[8 * j + 6], acc[8 * j + 7]));
      stsm_x2(ln_stv + 768, 0x3f803f80u, 0x3f803f80u);
      {
        const uint8_t* mp = reinterpret_cast<const uint8_t*>(mask) + ((size_t)w * 4096 + (32 * (warp >> 1) + 4 * (warp & 1)) * 64) * 2 + ln_mask;
        ldg_stream(mk[0][0], mp);
        ldg_stream(mk[0][1], mp + 64);
        ldg_stream(mk[1][0], mp + 256);
        ldg_stream(mk[1][1], mp + 256 + 64);
      }
      if (FIRST) mbar_wait(sb + BAR_WQS, 0);
      wg_fence();
#pragma unroll
      for (int ks = 0; ks < 12; ks++) {
        wgmma_n96(acc, af[ks][0], af[ks][1], af[ks][2], af[ks][3], d_wq + ks * 64, ks != 0);
        if (ks + 1 == PASS_KSTEP && w + NCLUSTERS < NWIN) order_pass(BAR_ID_TOKEN + wg_next);
      }
      wg_commit();
      fence_async_smem();
      wg_bar(BAR_ID_WG + wg);
      wg_wait<0>();
      pin(acc);
#pragma unroll
      for (int i = 0; i < 24; i++) qf[i] = pack_bf16(acc[2 * i], acc[2 * i + 1]);
    }
    uint32_t of[2][12];
    if (FIRST && wg == 0) fetch_bias();
    {
      float s[2][32];
#pragma unroll
      for (int hh = 0; hh < 2; hh++) {
#pragma unroll
        for (int a = 0; a < 2; a++)
#pragma unroll
          for (int m = 0; m < 4; m++) {
            const int n = 4 * a + m;
            const uint32_t u0 = add_bf16x2(bz[hh][0][a][m], mk[0][a][m]), u1 = add_bf16x2(bz[hh][1][a][m], mk[1][a][m]);
            s[hh][4 * n + 0] = bf_lo(u0);
            s[hh][4 * n + 1] = bf_hi(u0);
            s[hh][4 * n + 2] = bf_lo(u1);
            s[hh][4 * n + 3] = bf_hi(u1);
          }
        wg_fence();
#pragma unroll
        for (int ks = 0; ks < 3; ks++)
          wgmma_n64(s[hh], qf[12 * hh + 4 * ks], qf[12 * hh + 4 * ks + 1], qf[12 * hh + 4 * ks + 2], qf[12 * hh + 4 * ks + 3],
                    d_k + (hh * 48 + ks * 16), 1);
        wg_commit();
      }
      float o[2][28];
      auto imax_part = [&](const float (&sc)[32], int n, int& m0, int& m1) {
        m0 = __vimax3_s32(m0, __float_as_int(sc[4 * n + 0]), __float_as_int(sc[4 * n + 1]));
        m1 = __vimax3_s32(m1, __float_as_int(sc[4 * n + 2]), __float_as_int(sc[4 * n + 3]));
      };
      auto max_finish = [&](const float (&sc)[32], int m0, int m1, float& c0, float& c1) {
        int t0 = __shfl_xor_sync(0xffffffffu, m0, 1), t1 = __shfl_xor_sync(0xffffffffu, m1, 1);
        m0 = max(m0, t0);
        m1 = max(m1, t1);
        t0 = __shfl_xor_sync(0xffffffffu, m0, 2);
        t1 = __shfl_xor_sync(0xffffffffu, m1, 2);
        m0 = max(m0, t0);
        m1 = max(m1, t1);
        float mx0 = __int_as_float(m0), mx1 = __int_as_float(m1);
        if (__any_sync(0xffffffffu, (m0 | m1) < 0)) {
          mx0 = fmaxf(sc[0], sc[1]);
          mx1 = fmaxf(sc[2], sc[3]);
#pragma unroll
          for (int n = 1; n < 8; n++) {
            mx0 = fmaxf(mx0, fmaxf(sc[4 * n + 0], sc[4 * n + 1]));
            mx1 = fmaxf(mx1, fmaxf(sc[4 * n + 2], sc[4 * n + 3]));
          }
          mx0 = fmaxf(mx0, __shfl_xor_sync(0xffffffffu, mx0, 1));
          mx1 = fmaxf(mx1, __shfl_xor_sync(0xffffffffu, mx1, 1));
          mx0 = fmaxf(mx0, __shfl_xor_sync(0xffffffffu, mx0, 2));
          mx1 = fmaxf(mx1, __shfl_xor_sync(0xffffffffu, mx1, 2));
        }
        c0 = mx0 * -LOG2E;
        c1 = mx1 * -LOG2E;
      };
      auto pv = [&](int hh, const uint32_t (&pf)[16]) {
        wg_fence();
#pragma unroll
        for (int ks = 0; ks < 4; ks++)
          wgmma_n56(o[hh], pf[4 * ks], pf[4 * ks + 1], pf[4 * ks + 2], pf[4 * ks + 3], d_v + (hh * 48 + ks * (2 * VTB / 16)), ks != 0);
        wg_commit();
      };
      float c0, c1;
      wg_wait<1>();
      pin(s[0]);
      {
        int m0 = INT_MIN, m1 = INT_MIN;
#pragma unroll
        for (int n = 0; n < 8; n++) imax_part(s[0], n, m0, m1);
        max_finish(s[0], m0, m1, c0, c1);
      }
      wg_wait<0>();
      pin(s[1]);
      if (elect_one()) mbar_arrive_remote(map_peer(bar_kfree, peer));
      int m10 = INT_MIN, m11 = INT_MIN;
      {
        uint32_t pf[16];
#pragma unroll
        for (int n = 0; n < 8; n++) {
          pf[2 * n] = pack_bf16(ex2(fmaf(s[0][4 * n + 0], LOG2E, c0)), ex2(fmaf(s[0][4 * n + 1], LOG2E, c0)));
          pf[2 * n + 1] = pack_bf16(ex2(fmaf(s[0][4 * n + 2], LOG2E, c1)), ex2(fmaf(s[0][4 * n + 3], LOG2E, c1)));
          imax_part(s[1], n, m10, m11);
        }
        if (w + NCLUSTERS < NWIN) order_wait(BAR_ID_GAP + wg_next);
        pv(0, pf);
      }
      const uint32_t pslot = map_peer(ln_slot, peer);
      auto finish_head = [&](int hh) {
        pin(o[hh]);
        const float* oo = &o[hh][hh == 0 ? 0 : 4];
        const float* rs = &o[hh][hh == 0 ? 24 : 0];
        const float r0 = rcp(rs[0]), r1 = rcp(rs[2]);
#pragma unroll
        for (int n = 0; n < 6; n++) {
          of[hh][2 * n] = pack_bf16(oo[4 * n] * r0, oo[4 * n + 1] * r0);
          of[hh][2 * n + 1] = pack_bf16(oo[4 * n + 2] * r1, oo[4 * n + 3] * r1);
        }
        const uint32_t pbar = map_peer(bar_ofull + hh * 8, peer);
        if (hh == 0) mbar_wait(bar_kfree, parity);
#pragma unroll
        for (int c = 0; c < 3; c++) st_async_v4(pslot + (3 * hh + c) * 512, of[hh][4 * c], of[hh][4 * c + 1], of[hh][4 * c + 2], of[hh][4 * c + 3], pbar);
      };
      max_finish(s[1], m10, m11, c0, c1);
      wg_wait<0>();
      finish_head(0);
      {
        uint32_t pf[16];
#pragma unroll
        for (int n = 0; n < 8; n++) {
          pf[2 * n] = pack_bf16(ex2(fmaf(s[1][4 * n + 0], LOG2E, c0)), ex2(fmaf(s[1][4 * n + 1], LOG2E, c0)));
          pf[2 * n + 1] = pack_bf16(ex2(fmaf(s[1][4 * n + 2], LOG2E, c1)), ex2(fmaf(s[1][4 * n + 3], LOG2E, c1)));
        }
        pv(1, pf);
      }
      wg_wait<0>();
      finish_head(1);
    }
    float po[48];
    {
      uint32_t pe[6][4];
      if (FIRST) mbar_wait(sb + BAR_WO, 0);
      mbar_wait(bar_ofull, parity);
#pragma unroll
      for (int c = 0; c < 3; c++) lds_v4(pe[c], ln_slot + c * 512);
      wg_fence();
#pragma unroll
      for (int ks = 0; ks < 6; ks++) {
        const uint32_t* f = &of[ks / 3][4 * (ks % 3)];
        wgmma_n96(po, f[0], f[1], f[2], f[3], d_wo_own + ks * 64, ks != 0);
      }
#pragma unroll
      for (int ks = 0; ks < 3; ks++) wgmma_n96(po, pe[ks][0], pe[ks][1], pe[ks][2], pe[ks][3], d_wo_peer + ks * 64, 1);
      wg_commit();
      wg_bar(BAR_ID_WG + wg);
      mbar_wait(bar_ofull + 8, parity);
#pragma unroll
      for (int c = 3; c < 6; c++) lds_v4(pe[c], ln_slot + c * 512);
      wg_fence();
#pragma unroll
      for (int ks = 3; ks < 6; ks++) wgmma_n96(po, pe[ks][0], pe[ks][1], pe[ks][2], pe[ks][3], d_wo_peer + ks * 64, 1);
      wg_commit();
      if (elect_one() && has_next) stage_x(&tmx, nwi, nwj, warp, kbase, bar_x);
    }
    wg_wait<0>();
    pin(po);
#pragma unroll
    for (int i = 0; i < 24; i++) ob[i] = pack_bf16(po[2 * i], po[2 * i + 1]);
    pwi = wi; pwj = wj;
    wi = nwi; wj = nwj;
    parity ^= 1;
    w += WSTEP;
  };
  window(TrueTag{});
  while (w < NWIN) window(FalseTag{});
  store_out(pwi, pwj);
  if (elect_one()) asm volatile("cp.async.bulk.wait_group 0;" ::: "memory");
  asm volatile("barrier.cluster.arrive.relaxed.aligned;" ::: "memory");
  asm volatile("barrier.cluster.wait.aligned;" ::: "memory");
}

typedef CUresult (*EncodeTiledFn)(CUtensorMap*, CUtensorMapDataType, cuuint32_t, void*, const cuuint64_t*, const cuuint64_t*, const cuuint32_t*,
                                  const cuuint32_t*, CUtensorMapInterleave, CUtensorMapSwizzle, CUtensorMapL2promotion, CUtensorMapFloatOOBfill);

}


extern "C" void kernel_launch(void* const* d_in, const int* in_sizes, int n_in, void* d_out, int out_size) {
  (void)in_sizes; (void)n_in; (void)out_size;
  const __nv_bfloat16* x = (const __nv_bfloat16*)d_in[0];
  const __nv_bfloat16* wqkv = (const __nv_bfloat16*)d_in[1];
  const __nv_bfloat16* wo = (const __nv_bfloat16*)d_in[2];
  const __nv_bfloat16* rpb = (const __nv_bfloat16*)d_in[3];
  const int* rp_idx = (const int*)d_in[4];
  const __nv_bfloat16* mask = (const __nv_bfloat16*)d_in[5];
  static EncodeTiledFn encode = nullptr;
  if (!encode) {
    void* fn = nullptr;
    cudaDriverEntryPointQueryResult st;
    cudaGetDriverEntryPoint("cuTensorMapEncodeTiled", &fn, cudaEnableDefault, &st);
    encode = (EncodeTiledFn)fn;
    cudaFuncSetAttribute(swin_attn_kernel, cudaFuncAttributeMaxDynamicSharedMemorySize, SMEM_BYTES);
  }
  CUtensorMap tmx, tmw;
  {
    cuuint64_t dims[5] = {64, 2, IMG, IMG / 2, 3};
    cuuint64_t strides[4] = {CH * 2, (cuuint64_t)IMG * CH * 2, 2 * CH * 2, 128};
    cuuint32_t box[5] = {64, 2, 4, 1, 3};
    cuuint32_t es[5] = {1, 1, 1, 1, 1};
    encode(&tmx, CU_TENSOR_MAP_DATA_TYPE_BFLOAT16, 5, (void*)x, dims, strides, box, es, CU_TENSOR_MAP_INTERLEAVE_NONE, CU_TENSOR_MAP_SWIZZLE_128B,
           CU_TENSOR_MAP_L2_PROMOTION_L2_128B, CU_TENSOR_MAP_FLOAT_OOB_FILL_NONE);
  }
  {
    cuuint64_t dims[2] = {3 * CH, CH};
    cuuint64_t strides[1] = {3 * CH * 2};
    cuuint32_t box[2] = {32, CH};
    cuuint32_t es[2] = {1, 1};
    encode(&tmw, CU_TENSOR_MAP_DATA_TYPE_BFLOAT16, 2, (void*)wqkv, dims, strides, box, es, CU_TENSOR_MAP_INTERLEAVE_NONE, CU_TENSOR_MAP_SWIZZLE_64B,
           CU_TENSOR_MAP_L2_PROMOTION_L2_128B, CU_TENSOR_MAP_FLOAT_OOB_FILL_NONE);
  }
  CUtensorMap tmo, tmy0, tmy1;
  {
    cuuint64_t dims[2] = {CH, CH};
    cuuint64_t strides[1] = {CH * 2};
    cuuint32_t box[2] = {32, CH};
    cuuint32_t es[2] = {1, 1};
    encode(&tmo, CU_TENSOR_MAP_DATA_TYPE_BFLOAT16, 2, (void*)wo, dims, strides, box, es, CU_TENSOR_MAP_INTERLEAVE_NONE, CU_TENSOR_MAP_SWIZZLE_64B,
           CU_TENSOR_MAP_L2_PROMOTION_L2_128B, CU_TENSOR_MAP_FLOAT_OOB_FILL_NONE);
  }
  for (int i = 0; i < 2; i++) {
    cuuint64_t dims[4] = {CH, 2, IMG, IMG / 2};
    cuuint64_t strides[3] = {CH * 2, (cuuint64_t)IMG * CH * 2, 2 * CH * 2};
    cuuint32_t box[4] = {i == 0 ? 64u : 32u, 2, 4, 2};
    cuuint32_t es[4] = {1, 1, 1, 1};
    encode(i == 0 ? &tmy0 : &tmy1, CU_TENSOR_MAP_DATA_TYPE_BFLOAT16, 4, d_out, dims, strides, box, es, CU_TENSOR_MAP_INTERLEAVE_NONE,
           i == 0 ? CU_TENSOR_MAP_SWIZZLE_128B : CU_TENSOR_MAP_SWIZZLE_64B, CU_TENSOR_MAP_L2_PROMOTION_NONE, CU_TENSOR_MAP_FLOAT_OOB_FILL_NONE);
  }
  swin_attn_kernel<<<2 * NCLUSTERS, NTHREADS, SMEM_BYTES>>>(tmx, tmw, tmo, tmy0, tmy1, rpb, rp_idx, mask);
}
```
